```python
import torch

def _softmax(x, axis=-1):
    return torch.softmax(x, dim=axis)
def _gelu(x):
    return torch.nn.functional.gelu(x, approximate="tanh")
def _silu(x):
    return torch.nn.functional.silu(x)
def _sigmoid(x):
    return torch.sigmoid(x)
def _layernorm(x, axis=-1, eps=1e-5):
    m = x.mean(dim=axis, keepdim=True)
    v = x.var(dim=axis, keepdim=True, unbiased=False)
    return (x - m) / torch.sqrt(v + eps)
def _scatter_add(tgt, idx, src, axis=0):
    return tgt.clone().index_add_(axis, idx, src)
def _segment_sum(src, seg, n):
    out = torch.zeros((n,) + src.shape[1:], dtype=src.dtype)
    return out.index_add_(0, seg, src)
def _pad(x, pw):
    flat = tuple(v for pair in reversed(pw) for v in pair)
    return torch.nn.functional.pad(x, flat)

kernel_name = 'parallel_sum__ssm_conv_s5__glu_gated_swiglu__prompt'

def setup_inputs():

    _w = (lambda a: (lambda t: t.to(torch.bfloat16) if t.is_floating_point() else t)(torch.as_tensor(a)))
    def _A_setup():
        B, S, D = 1, 2048, 576
        P = D
        Lambda_re = -0.5 * (lambda _x: torch.exp(torch.as_tensor(_x)))((lambda *s: torch.randn(*s, dtype=torch.bfloat16) * 0.2)(P))
        Lambda_im = (lambda *s: torch.randn(*s, dtype=torch.bfloat16) * 0.8)(P) * 1.0
        B_re = (lambda *s: torch.randn(*s, dtype=torch.bfloat16) * 0.2)(P, D) * (D ** -0.5)
        B_im = (lambda *s: torch.randn(*s, dtype=torch.bfloat16) * 0.2)(P, D) * (D ** -0.5)
        C_re = (lambda *s: torch.randn(*s, dtype=torch.bfloat16) * 0.2)(D, P) * (P ** -0.5)
        C_im = (lambda *s: torch.randn(*s, dtype=torch.bfloat16) * 0.2)(D, P) * (P ** -0.5)
        log_dt = (lambda *s: torch.randn(*s, dtype=torch.bfloat16) * 0.2)(P) * 0.3 - 2.0
        Dskip = (lambda *s: torch.randn(*s, dtype=torch.bfloat16) * 0.05)(D)
        return {
            "x": _w((lambda *s: torch.randn(*s, dtype=torch.bfloat16) * 0.05)(B, S, D)),
            "Lambda_re": _w(Lambda_re),
            "Lambda_im": _w(Lambda_im),
            "B_re": _w(B_re),
            "B_im": _w(B_im),
            "C_re": _w(C_re),
            "C_im": _w(C_im),
            "log_dt": _w(log_dt),
            "Dskip": _w(Dskip),
        }
    _A_in = _A_setup()

    def _B_setup():
        B, S, D, F = 1, 2048, 576, 4608
        return {
            "x": _w((lambda *s: torch.randn(*s, dtype=torch.bfloat16) * 0.05)(B, S, D)),
            "w1": _w((lambda *s: torch.randn(*s, dtype=torch.bfloat16) * 0.4)(D, F) * (2.0 / D) ** 0.5),
            "w3": _w((lambda *s: torch.randn(*s, dtype=torch.bfloat16) * 0.4)(D, F) * (2.0 / D) ** 0.5),
            "w2": _w((lambda *s: torch.randn(*s, dtype=torch.bfloat16) * 0.4)(F, D) * (2.0 / F) ** 0.5),
        }
    _B_in = _B_setup()

    return {
        "A_x": _A_in["x"],
        "A_Lambda_re": _A_in["Lambda_re"],
        "A_Lambda_im": _A_in["Lambda_im"],
        "A_B_re": _A_in["B_re"],
        "A_B_im": _A_in["B_im"],
        "A_C_re": _A_in["C_re"],
        "A_C_im": _A_in["C_im"],
        "A_log_dt": _A_in["log_dt"],
        "A_Dskip": _A_in["Dskip"],
        "B_x": _B_in["x"],
        "B_w1": _B_in["w1"],
        "B_w3": _B_in["w3"],
        "B_w2": _B_in["w2"],
    }

def reference(A_x, A_Lambda_re, A_Lambda_im, A_B_re, A_B_im, A_C_re, A_C_im, A_log_dt, A_Dskip, B_x, B_w1, B_w3, B_w2):
    def _A_ref(x, Lambda_re, Lambda_im, B_re, B_im, C_re, C_im, log_dt, Dskip):
        Bsz, L, H = x.shape
        Lam = Lambda_re + 1j * Lambda_im
        Bmat = B_re + 1j * B_im
        Cmat = C_re + 1j * C_im
        dt = torch.exp(log_dt)
        Lam_bar = torch.exp(dt * Lam)
        B_bar = ((Lam_bar - 1.0) / Lam)[:, None] * Bmat
        Bu = torch.einsum("bld,pd->blp", x + 0j, B_bar)
        h = torch.zeros_like(Bu[:, 0, :])
        hs = []
        for t in range(L):
            h = Lam_bar[None, :] * h + Bu[:, t, :]
            hs.append(h)
        hseq = torch.stack(hs, 1)
        y = 2.0 * torch.einsum("blp,dp->bld", hseq, Cmat).real + x * Dskip[None, None, :]
        return y

    def _B_ref(x, w1, w3, w2):
        gate = torch.einsum("bsd,df->bsf", x, w1)
        up = torch.einsum("bsd,df->bsf", x, w3)
        h = _silu(gate) * up
        out = torch.einsum("bsf,fd->bsd", h, w2)
        return out

    x = A_x
    xn = _layernorm(x, axis=-1)
    return x + _A_ref(xn, A_Lambda_re, A_Lambda_im, A_B_re, A_B_im, A_C_re, A_C_im, A_log_dt, A_Dskip) + _B_ref(xn, B_w1, B_w3, B_w2)
```

```cpp
#include <cuda_runtime.h>
#include <cuda_bf16.h>
#include <cuda.h>
#include <stdint.h>

namespace {

template <int TB>
__device__ __forceinline__ void wgmma_rs_n128(float (&d)[64], uint32_t a0, uint32_t a1, uint32_t a2, uint32_t a3, uint64_t db, int sd) {
  asm volatile("{\n.reg .pred p;\n"
    "setp.ne.b32 p, %69, 0;\n"
    "wgmma.mma_async.sync.aligned.m64n128k16.f32.bf16.bf16 "
    "{%0, %1, %2, %3, %4, %5, %6, %7, %8, %9, %10, %11, %12, %13, %14, %15, "
    "%16, %17, %18, %19, %20, %21, %22, %23, %24, %25, %26, %27, %28, %29, %30, %31, "
    "%32, %33, %34, %35, %36, %37, %38, %39, %40, %41, %42, %43, %44, %45, %46, %47, "
    "%48, %49, %50, %51, %52, %53, %54, %55, %56, %57, %58, %59, %60, %61, %62, %63}, "
    "{%64, %65, %66, %67}, %68, p, 1, 1, %70;\n}\n"
    : "+f"(d[0]), "+f"(d[1]), "+f"(d[2]), "+f"(d[3]), "+f"(d[4]), "+f"(d[5]), "+f"(d[6]), "+f"(d[7]),
      "+f"(d[8]), "+f"(d[9]), "+f"(d[10]), "+f"(d[11]), "+f"(d[12]), "+f"(d[13]), "+f"(d[14]), "+f"(d[15]),
      "+f"(d[16]), "+f"(d[17]), "+f"(d[18]), "+f"(d[19]), "+f"(d[20]), "+f"(d[21]), "+f"(d[22]), "+f"(d[23]),
      "+f"(d[24]), "+f"(d[25]), "+f"(d[26]), "+f"(d[27]), "+f"(d[28]), "+f"(d[29]), "+f"(d[30]), "+f"(d[31]),
      "+f"(d[32]), "+f"(d[33]), "+f"(d[34]), "+f"(d[35]), "+f"(d[36]), "+f"(d[37]), "+f"(d[38]), "+f"(d[39]),
      "+f"(d[40]), "+f"(d[41]), "+f"(d[42]), "+f"(d[43]), "+f"(d[44]), "+f"(d[45]), "+f"(d[46]), "+f"(d[47]),
      "+f"(d[48]), "+f"(d[49]), "+f"(d[50]), "+f"(d[51]), "+f"(d[52]), "+f"(d[53]), "+f"(d[54]), "+f"(d[55]),
      "+f"(d[56]), "+f"(d[57]), "+f"(d[58]), "+f"(d[59]), "+f"(d[60]), "+f"(d[61]), "+f"(d[62]), "+f"(d[63])
    : "r"(a0), "r"(a1), "r"(a2), "r"(a3), "l"(db), "r"(sd), "n"(TB));
}

template <int TA, int TB>
__device__ __forceinline__ void wgmma_ss_n128(float (&d)[64], uint64_t da, uint64_t db, int sd) {
  asm volatile("{\n.reg .pred p;\n"
    "setp.ne.b32 p, %66, 0;\n"
    "wgmma.mma_async.sync.aligned.m64n128k16.f32.bf16.bf16 "
    "{%0, %1, %2, %3, %4, %5, %6, %7, %8, %9, %10, %11, %12, %13, %14, %15, "
    "%16, %17, %18, %19, %20, %21, %22, %23, %24, %25, %26, %27, %28, %29, %30, %31, "
    "%32, %33, %34, %35, %36, %37, %38, %39, %40, %41, %42, %43, %44, %45, %46, %47, "
    "%48, %49, %50, %51, %52, %53, %54, %55, %56, %57, %58, %59, %60, %61, %62, %63}, "
    "%64, %65, p, 1, 1, %67, %68;\n}\n"
    : "+f"(d[0]), "+f"(d[1]), "+f"(d[2]), "+f"(d[3]), "+f"(d[4]), "+f"(d[5]), "+f"(d[6]), "+f"(d[7]),
      "+f"(d[8]), "+f"(d[9]), "+f"(d[10]), "+f"(d[11]), "+f"(d[12]), "+f"(d[13]), "+f"(d[14]), "+f"(d[15]),
      "+f"(d[16]), "+f"(d[17]), "+f"(d[18]), "+f"(d[19]), "+f"(d[20]), "+f"(d[21]), "+f"(d[22]), "+f"(d[23]),
      "+f"(d[24]), "+f"(d[25]), "+f"(d[26]), "+f"(d[27]), "+f"(d[28]), "+f"(d[29]), "+f"(d[30]), "+f"(d[31]),
      "+f"(d[32]), "+f"(d[33]), "+f"(d[34]), "+f"(d[35]), "+f"(d[36]), "+f"(d[37]), "+f"(d[38]), "+f"(d[39]),
      "+f"(d[40]), "+f"(d[41]), "+f"(d[42]), "+f"(d[43]), "+f"(d[44]), "+f"(d[45]), "+f"(d[46]), "+f"(d[47]),
      "+f"(d[48]), "+f"(d[49]), "+f"(d[50]), "+f"(d[51]), "+f"(d[52]), "+f"(d[53]), "+f"(d[54]), "+f"(d[55]),
      "+f"(d[56]), "+f"(d[57]), "+f"(d[58]), "+f"(d[59]), "+f"(d[60]), "+f"(d[61]), "+f"(d[62]), "+f"(d[63])
    : "l"(da), "l"(db), "r"(sd), "n"(TA), "n"(TB));
}

template <int TA, int TB>
__device__ __forceinline__ void wgmma_ss_n144(float (&d)[72], uint64_t da, uint64_t db, int sd) {
  asm volatile("{\n.reg .pred p;\n"
    "setp.ne.b32 p, %74, 0;\n"
    "wgmma.mma_async.sync.aligned.m64n144k16.f32.bf16.bf16 "
    "{%0, %1, %2, %3, %4, %5, %6, %7, %8, %9, %10, %11, %12, %13, %14, %15, "
    "%16, %17, %18, %19, %20, %21, %22, %23, %24, %25, %26, %27, %28, %29, %30, %31, "
    "%32, %33, %34, %35, %36, %37, %38, %39, %40, %41, %42, %43, %44, %45, %46, %47, "
    "%48, %49, %50, %51, %52, %53, %54, %55, %56, %57, %58, %59, %60, %61, %62, %63, "
    "%64, %65, %66, %67, %68, %69, %70, %71}, "
    "%72, %73, p, 1, 1, %75, %76;\n}\n"
    : "+f"(d[0]), "+f"(d[1]), "+f"(d[2]), "+f"(d[3]), "+f"(d[4]), "+f"(d[5]), "+f"(d[6]), "+f"(d[7]),
      "+f"(d[8]), "+f"(d[9]), "+f"(d[10]), "+f"(d[11]), "+f"(d[12]), "+f"(d[13]), "+f"(d[14]), "+f"(d[15]),
      "+f"(d[16]), "+f"(d[17]), "+f"(d[18]), "+f"(d[19]), "+f"(d[20]), "+f"(d[21]), "+f"(d[22]), "+f"(d[23]),
      "+f"(d[24]), "+f"(d[25]), "+f"(d[26]), "+f"(d[27]), "+f"(d[28]), "+f"(d[29]), "+f"(d[30]), "+f"(d[31]),
      "+f"(d[32]), "+f"(d[33]), "+f"(d[34]), "+f"(d[35]), "+f"(d[36]), "+f"(d[37]), "+f"(d[38]), "+f"(d[39]),
      "+f"(d[40]), "+f"(d[41]), "+f"(d[42]), "+f"(d[43]), "+f"(d[44]), "+f"(d[45]), "+f"(d[46]), "+f"(d[47]),
      "+f"(d[48]), "+f"(d[49]), "+f"(d[50]), "+f"(d[51]), "+f"(d[52]), "+f"(d[53]), "+f"(d[54]), "+f"(d[55]),
      "+f"(d[56]), "+f"(d[57]), "+f"(d[58]), "+f"(d[59]), "+f"(d[60]), "+f"(d[61]), "+f"(d[62]), "+f"(d[63]),
      "+f"(d[64]), "+f"(d[65]), "+f"(d[66]), "+f"(d[67]), "+f"(d[68]), "+f"(d[69]), "+f"(d[70]), "+f"(d[71])
    : "l"(da), "l"(db), "r"(sd), "n"(TA), "n"(TB));
}

template <int TA, int TB>
__device__ __forceinline__ void wgmma_ss_n144_init(float (&d)[72], uint64_t da, uint64_t db) {
  asm volatile("{\n.reg .pred p;\n"
    "setp.ne.b32 p, %74, 0;\n"
    "wgmma.mma_async.sync.aligned.m64n144k16.f32.bf16.bf16 "
    "{%0, %1, %2, %3, %4, %5, %6, %7, %8, %9, %10, %11, %12, %13, %14, %15, "
    "%16, %17, %18, %19, %20, %21, %22, %23, %24, %25, %26, %27, %28, %29, %30, %31, "
    "%32, %33, %34, %35, %36, %37, %38, %39, %40, %41, %42, %43, %44, %45, %46, %47, "
    "%48, %49, %50, %51, %52, %53, %54, %55, %56, %57, %58, %59, %60, %61, %62, %63, "
    "%64, %65, %66, %67, %68, %69, %70, %71}, "
    "%72, %73, p, 1, 1, %75, %76;\n}\n"
    : "=f"(d[0]), "=f"(d[1]), "=f"(d[2]), "=f"(d[3]), "=f"(d[4]), "=f"(d[5]), "=f"(d[6]), "=f"(d[7]),
      "=f"(d[8]), "=f"(d[9]), "=f"(d[10]), "=f"(d[11]), "=f"(d[12]), "=f"(d[13]), "=f"(d[14]), "=f"(d[15]),
      "=f"(d[16]), "=f"(d[17]), "=f"(d[18]), "=f"(d[19]), "=f"(d[20]), "=f"(d[21]), "=f"(d[22]), "=f"(d[23]),
      "=f"(d[24]), "=f"(d[25]), "=f"(d[26]), "=f"(d[27]), "=f"(d[28]), "=f"(d[29]), "=f"(d[30]), "=f"(d[31]),
      "=f"(d[32]), "=f"(d[33]), "=f"(d[34]), "=f"(d[35]), "=f"(d[36]), "=f"(d[37]), "=f"(d[38]), "=f"(d[39]),
      "=f"(d[40]), "=f"(d[41]), "=f"(d[42]), "=f"(d[43]), "=f"(d[44]), "=f"(d[45]), "=f"(d[46]), "=f"(d[47]),
      "=f"(d[48]), "=f"(d[49]), "=f"(d[50]), "=f"(d[51]), "=f"(d[52]), "=f"(d[53]), "=f"(d[54]), "=f"(d[55]),
      "=f"(d[56]), "=f"(d[57]), "=f"(d[58]), "=f"(d[59]), "=f"(d[60]), "=f"(d[61]), "=f"(d[62]), "=f"(d[63]),
      "=f"(d[64]), "=f"(d[65]), "=f"(d[66]), "=f"(d[67]), "=f"(d[68]), "=f"(d[69]), "=f"(d[70]), "=f"(d[71])
    : "l"(da), "l"(db), "n"(0), "n"(TA), "n"(TB));
}

constexpr int SEQ = 2048, DM = 576, FF = 4608;
constexpr int NCL = 66;
constexpr int NGLU = 72;
constexpr int NCHUNK = 90;
constexpr int G2N = 144;
constexpr int MAXSEQ = 24;
constexpr uint32_t SPIN_LIMIT = 1u << 22;

constexpr uint32_t OFF_STG = 0;
constexpr uint32_t OFF_RING = 16384;
constexpr uint32_t G1_STAGE = 49152;
constexpr uint32_t OFF_XA = 212992;
constexpr uint32_t G2_STAGE = 40960;
constexpr uint32_t OFF_BAR = 229376;
constexpr uint32_t OFF_SIB = OFF_BAR + 1536;
constexpr uint32_t SMEM_BYTES = OFF_BAR + 2304;
constexpr uint32_t OUT_PITCH = 608;
constexpr uint32_t B_FULL1 = 0, B_EMPTY1 = 4, B_FULL2 = 8, B_EMPTY2 = 13, B_STGF = 18, B_STGD = 20;
#define PF_G2 2
#define LOOKAHEAD 6
#define SEG1 49

struct alignas(64) Params {
  CUtensorMap tm_x, tm_x16, tm_w1, tm_w3, tm_bre, tm_bim, tm_cp, tm_w2[4];
  const __nv_bfloat16 *x, *w2, *lam_re, *lam_im, *log_dt, *dskip, *c_re, *c_im;
  float* out;
  uint8_t seq[NCL][MAXSEQ];
  uint8_t nseq[NCL];
  int8_t g2tile[NCL];
  uint8_t lid[NCL];
  int zero;
};

__device__ uint4 g_h[16 * NCHUNK * 1024];
__device__ uint4 g_bu[32 * 18 * 512];
__device__ uint32_t g_cp[DM * DM];
__device__ unsigned long long g_agg[18 * 16 * 32];
__device__ float2 g_priv[576 * 4 * 32];
__device__ unsigned g_flag[16 * 96];
__device__ unsigned g_buflag[16 * 16];
__device__ unsigned g_cflag[32];
__device__ unsigned g_epoch[2 * NCL];
#define TL(role, idx) do { } while (0)
#define TG(role, idx) do { } while (0)

__device__ __forceinline__ uint32_t smem_u32(const void* p) { return (uint32_t)__cvta_generic_to_shared(p); }
__device__ __forceinline__ int lane_id() { int r; asm volatile("mov.u32 %0, %%laneid;" : "=r"(r)); return r; }
__device__ __forceinline__ void mbar_init(uint32_t bar, uint32_t cnt) {
  asm volatile("mbarrier.init.shared::cta.b64 [%0], %1;" ::"r"(bar), "r"(cnt));
}
__device__ __forceinline__ void mbar_arrive(uint32_t bar) {
  asm volatile("mbarrier.arrive.shared::cta.b64 _, [%0];" ::"r"(bar) : "memory");
}
__device__ __forceinline__ void mbar_arrive_cl(uint32_t bar, uint32_t cta) {
  asm volatile("{\n.reg .b32 ra;\nmapa.shared::cluster.u32 ra, %0, %1;\n"
               "mbarrier.arrive.shared::cluster.b64 _, [ra];\n}\n" ::"r"(bar), "r"(cta) : "memory");
}
__device__ __forceinline__ uint32_t map_cta(uint32_t addr, uint32_t cta) {
  uint32_t r;
  asm("mapa.shared::cluster.u32 %0, %1, %2;" : "=r"(r) : "r"(addr), "r"(cta));
  return r;
}
__device__ __forceinline__ void mbar_arrive_at(uint32_t cluster_addr) {
  asm volatile("mbarrier.arrive.shared::cluster.b64 _, [%0];" ::"r"(cluster_addr) : "memory");
}
__device__ __forceinline__ void mbar_wait(uint32_t bar, uint32_t parity) {
  asm volatile("{\n.reg .pred p;\n.reg .u32 c;\nmov.u32 c, 0;\n"
               "LAB_WAIT:\nmbarrier.try_wait.parity.shared::cta.b64 p, [%0], %1;\n@p bra LAB_DONE;\n"
               "add.u32 c, c, 1;\nsetp.lt.u32 p, c, %2;\n@p bra LAB_WAIT;\ntrap;\nLAB_DONE:\n}\n"
               ::"r"(bar), "r"(parity), "n"(SPIN_LIMIT) : "memory");
}
__device__ __forceinline__ void wait_count(uint32_t addr, int n) {
  asm volatile("{\n.reg .pred p;\n.reg .u32 c, v;\nmov.u32 c, 0;\n"
               "LAB_WAIT:\nld.acquire.cta.shared.u32 v, [%0];\nsetp.ge.s32 p, v, %1;\n@p bra LAB_DONE;\n"
               "add.u32 c, c, 1;\nsetp.lt.u32 p, c, %2;\n@p bra LAB_WAIT;\ntrap;\nLAB_DONE:\n}\n"
               ::"r"(addr), "r"(n), "n"(SPIN_LIMIT * 4) : "memory");
}
constexpr uint64_t EVICT_FIRST = 0x12F0000000000000ull;
#define HINT
#define HINTOP(n)
#define HINT1
#define HINTOP1(n)
__device__ __forceinline__ void e_expect_tx(uint32_t bar, uint32_t bytes) {
  asm volatile("{\n.reg .pred p;\nelect.sync _|p, 0xffffffff;\n"
               "@p mbarrier.arrive.expect_tx.shared::cta.b64 _, [%0], %1;\n}\n" ::"r"(bar), "r"(bytes) : "memory");
}
__device__ __forceinline__ void e_tma(uint32_t dst, const CUtensorMap* tm, uint32_t bar, int c0, int c1) {
  asm volatile("{\n.reg .pred p;\nelect.sync _|p, 0xffffffff;\n"
               "@p cp.async.bulk.tensor.2d.shared::cluster.global.mbarrier::complete_tx::bytes [%0], [%1, {%3, %4}], [%2];\n}\n"
               ::"r"(dst), "l"(tm), "r"(bar), "r"(c0), "r"(c1) : "memory");
}
__device__ __forceinline__ void e_tma_mc(uint32_t dst, const CUtensorMap* tm, uint32_t bar, int c0, int c1) {
  asm volatile("{\n.reg .pred p;\n.reg .b16 m;\nmov.b16 m, 3;\nelect.sync _|p, 0xffffffff;\n"
               "@p cp.async.bulk.tensor.2d.shared::cluster.global.mbarrier::complete_tx::bytes.multicast::cluster" HINT1
               " [%0], [%1, {%3, %4}], [%2], m" HINTOP1(5) ";\n}\n"
               ::"r"(dst), "l"(tm), "r"(bar), "r"(c0), "r"(c1), "l"(EVICT_FIRST) : "memory");
}
__device__ __forceinline__ void e_bulk_ld(uint32_t dst, const void* src, uint32_t bytes, uint32_t bar) {
  asm volatile("{\n.reg .pred p;\nelect.sync _|p, 0xffffffff;\n"
               "@p cp.async.bulk.shared::cluster.global.mbarrier::complete_tx::bytes [%0], [%1], %2, [%3];\n}\n"
               ::"r"(dst), "l"(src), "r"(bytes), "r"(bar) : "memory");
}
__device__ __forceinline__ void e_g2_glu(uint32_t st, uint32_t bdst, uint32_t bar, const void* hsrc, const CUtensorMap* tm, int c0, int c1) {
  asm volatile("{\n.reg .pred p;\n.reg .b16 m;\n.reg .b32 d, c;\nmov.b16 m, 3;\nelect.sync _|p, 0xffffffff;\n"
               "@p mbarrier.arrive.expect_tx.shared::cta.b64 _, [%2], 40960;\n"
               "@p cp.async.bulk.shared::cluster.global.mbarrier::complete_tx::bytes [%0], [%3], 16384, [%2];\n"
               "@p cp.async.bulk.tensor.2d.shared::cluster.global.mbarrier::complete_tx::bytes.multicast::cluster" HINT " [%1], [%4, {%5, %6}], [%2], m" HINTOP(7) ";\n"
               "add.u32 d, %1, 8192;\nadd.s32 c, %5, 64;\n"
               "@p cp.async.bulk.tensor.2d.shared::cluster.global.mbarrier::complete_tx::bytes.multicast::cluster" HINT " [d], [%4, {c, %6}], [%2], m" HINTOP(7) ";\n"
               "add.u32 d, %1, 16384;\nadd.s32 c, %5, 128;\n"
               "@p cp.async.bulk.tensor.2d.shared::cluster.global.mbarrier::complete_tx::bytes.multicast::cluster" HINT " [d], [%4, {c, %6}], [%2], m" HINTOP(7) ";\n}\n"
               ::"r"(st), "r"(bdst), "r"(bar), "l"(hsrc), "l"(tm), "r"(c0), "r"(c1), "l"(EVICT_FIRST) : "memory");
}
__device__ __forceinline__ void e_g2_ssm(uint32_t st, uint32_t bdst, uint32_t bar, const void* hsrc, const CUtensorMap* tm, int c0, int c1) {
  asm volatile("{\n.reg .pred p;\n.reg .b16 m;\nmov.b16 m, 3;\nelect.sync _|p, 0xffffffff;\n"
               "@p mbarrier.arrive.expect_tx.shared::cta.b64 _, [%2], 34816;\n"
               "@p cp.async.bulk.shared::cluster.global.mbarrier::complete_tx::bytes [%0], [%3], 16384, [%2];\n"
               "@p cp.async.bulk.tensor.2d.shared::cluster.global.mbarrier::complete_tx::bytes.multicast::cluster [%1], [%4, {%5, %6}], [%2], m;\n}\n"
               ::"r"(st), "r"(bdst), "r"(bar), "l"(hsrc), "l"(tm), "r"(c0), "r"(c1) : "memory");
}
template <bool ALL>
__device__ __forceinline__ uint32_t poll_flags(const unsigned* f, unsigned target) {
  uint32_t m;
  asm volatile("{\n.reg .pred p;\n.reg .u32 c, v;\nmov.u32 c, 0;\n"
               "LAB_POLL:\nld.acquire.gpu.global.u32 v, [%1];\nsub.u32 v, v, %2;\nsetp.ge.s32 p, v, 0;\n"
               "vote.sync.ballot.b32 %0, p, 0xffffffff;\nand.b32 v, %0, %3;\nsetp.eq.u32 p, v, %3;\n@p bra.uni LAB_OK;\n"
               "nanosleep.u32 100;\nadd.u32 c, c, 1;\nsetp.lt.u32 p, c, %4;\n@p bra.uni LAB_POLL;\ntrap;\nLAB_OK:\n"
               "fence.proxy.async.global;\n}\n"
               : "=r"(m) : "l"(f), "r"(target), "n"(ALL ? 0xffffffffu : 1u), "n"(SPIN_LIMIT) : "memory");
  return m;
}
__device__ __forceinline__ void e_prefetch(const void* src, uint32_t bytes) {
  asm volatile("{\n.reg .pred p;\nelect.sync _|p, 0xffffffff;\n@p cp.async.bulk.prefetch.L2.global [%0], %1;\n}\n" ::"l"(src), "r"(bytes) : "memory");
}
__device__ __forceinline__ uint64_t make_desc(uint32_t addr, uint32_t lbo, uint32_t sbo) {
  return (uint64_t)((addr & 0x3FFFF) >> 4) | ((uint64_t)(lbo >> 4) << 16) | ((uint64_t)(sbo >> 4) << 32) | (1ull << 62);
}
__device__ __forceinline__ void wg_fence() { asm volatile("wgmma.fence.sync.aligned;" ::: "memory"); }
__device__ __forceinline__ void wg_commit() { asm volatile("wgmma.commit_group.sync.aligned;" ::: "memory"); }
template <int N> __device__ __forceinline__ void wg_wait() { asm volatile("wgmma.wait_group.sync.aligned %0;" ::"n"(N) : "memory"); }
template <int N> __device__ __forceinline__ void pin(float (&d)[N]) {
#pragma unroll
  for (int i = 0; i < N; i++) asm volatile("" : "+f"(d[i])::"memory");
}
template <int N> __device__ __forceinline__ void pin(uint32_t (&d)[N]) {
#pragma unroll
  for (int i = 0; i < N; i++) asm volatile("" : "+r"(d[i])::"memory");
}
template <int N, int M> __device__ __forceinline__ void pin2(uint32_t (&d)[N][M]) {
#pragma unroll
  for (int i = 0; i < N; i++) pin(d[i]);
}
__device__ __forceinline__ void bar_sync(uint32_t id, uint32_t n) { asm volatile("bar.sync %0, %1;" ::"r"(id), "r"(n) : "memory"); }
__device__ __forceinline__ void bar_arrive(uint32_t id, uint32_t n) { asm volatile("bar.arrive %0, %1;" ::"r"(id), "r"(n) : "memory"); }
__device__ __forceinline__ void fence_async_gl() { asm volatile("fence.proxy.async.global;" ::: "memory"); }
__device__ __forceinline__ void fence_gpu() { asm volatile("fence.acq_rel.gpu;" ::: "memory"); }
__device__ __forceinline__ void red_relaxed(unsigned* p, unsigned v) {
  asm volatile("red.relaxed.gpu.global.add.u32 [%0], %1;" ::"l"(p), "r"(v) : "memory");
}
__device__ __forceinline__ void fence_async_smem() { asm volatile("fence.proxy.async.shared::cta;" ::: "memory"); }
__device__ __forceinline__ void cluster_arrive() { asm volatile("barrier.cluster.arrive.relaxed;" ::: "memory"); }
__device__ __forceinline__ void cluster_wait() { asm volatile("barrier.cluster.wait;" ::: "memory"); }
__device__ __forceinline__ void prefetch_map(const CUtensorMap* tm) {
  asm volatile("prefetch.tensormap [%0];" ::"l"(tm) : "memory");
}
__device__ __forceinline__ unsigned ld_acquire(const unsigned* p) {
  unsigned v;
  asm volatile("ld.acquire.gpu.global.u32 %0, [%1];" : "=r"(v) : "l"(p) : "memory");
  return v;
}
__device__ __forceinline__ void red_release(unsigned* p, unsigned v) {
  asm volatile("red.release.gpu.global.add.u32 [%0], %1;" ::"l"(p), "r"(v) : "memory");
}
__device__ __forceinline__ void st_release(unsigned* p, unsigned v) {
  asm volatile("st.release.gpu.global.u32 [%0], %1;" ::"l"(p), "r"(v) : "memory");
}
__device__ __forceinline__ uint32_t pack_bf16(float lo, float hi) {
  uint32_t r;
  asm("cvt.rn.bf16x2.f32 %0, %1, %2;" : "=r"(r) : "f"(hi), "f"(lo));
  return r;
}
__device__ __forceinline__ float bf_lo(uint32_t v) { return __uint_as_float(v << 16); }
__device__ __forceinline__ float bf_hi(uint32_t v) { return __uint_as_float(v & 0xffff0000u); }
__device__ __forceinline__ float bf_round(float v) { return __bfloat162float(__float2bfloat16_rn(v)); }
__device__ __forceinline__ uint32_t sub_bf16x2(uint32_t a, uint32_t b) {
  uint32_t r;
  asm("sub.rn.bf16x2 %0, %1, %2;" : "=r"(r) : "r"(a), "r"(b));
  return r;
}
__device__ __forceinline__ float ex2(float v) { float r; asm("ex2.approx.ftz.f32 %0, %1;" : "=f"(r) : "f"(v)); return r; }
__device__ __forceinline__ float sqrt_fast(float v) { float r; asm("sqrt.approx.f32 %0, %1;" : "=f"(r) : "f"(v)); return r; }
__device__ __forceinline__ float rcp(float v) { float r; asm("rcp.approx.ftz.f32 %0, %1;" : "=f"(r) : "f"(v)); return r; }

__device__ __forceinline__ void mma16816(float (&c)[4], uint32_t a0, uint32_t a1, uint32_t a2, uint32_t a3, uint32_t b0, uint32_t b1) {
  asm("mma.sync.aligned.m16n8k16.row.col.f32.bf16.bf16.f32 {%0, %1, %2, %3}, {%4, %5, %6, %7}, {%8, %9}, {%0, %1, %2, %3};"
               : "+f"(c[0]), "+f"(c[1]), "+f"(c[2]), "+f"(c[3]) : "r"(a0), "r"(a1), "r"(a2), "r"(a3), "r"(b0), "r"(b1));
}

struct Ring {
  uint32_t l, ph, rot, base;
  __device__ __forceinline__ uint32_t ptr() const { return base + ((l + rot) & 3) * G1_STAGE; }
  __device__ __forceinline__ void next() { l = (l + 1) & 3; ph ^= (l == 0); }
};

template <int TB>
__device__ __forceinline__ void g1_mainloop(float (&acc)[64], uint32_t (&a)[128], Ring& r, uint32_t bars, uint32_t xa, int w,
                                            bool rel, uint32_t rbar, int tli) {
  uint32_t prev = 0;
  pin(acc);
#pragma unroll
  for (int j = 0; j < 3; j++) {
    mbar_wait(bars + 8 * (B_FULL1 + r.l), r.ph);
    wg_fence();
    const uint64_t d0 = TB ? make_desc(r.ptr(), 24576, 1024) : make_desc(r.ptr(), 16, 1024);
#pragma unroll
    for (int k = 0; k < 12; k++) {
      const uint64_t db = d0 + (TB ? 128 * k : (k >> 2) * 1024 + (k & 3) * 2);
      const int s = j * 12 + k;
      if (s < 32) wgmma_rs_n128<TB>(acc, a[4 * s], a[4 * s + 1], a[4 * s + 2], a[4 * s + 3], db, s != 0);
      else wgmma_ss_n128<0, TB>(acc, make_desc(xa, 16, 1024) + 2 * (s - 32), db, 1);
    }
    wg_commit();
    if (j == 0 && threadIdx.x % 128 == 0) TL(w, tli);
    if (j == 2) bar_arrive(1 + (w ^ 1), 256);
    if (j > 0) {
      wg_wait<1>();
      if (rel) mbar_arrive_at(prev);
    }
    prev = rbar + 8 * (B_EMPTY1 + r.l);
    r.next();
  }
  wg_wait<0>();
  if (rel) mbar_arrive_at(prev);
  pin(acc);
}

template <int TB, int S, bool FIRST = false, int PREV = (S + 4) % 5>
__device__ __forceinline__ void g2_step(float (&acc)[72], uint32_t ph, uint64_t da, uint64_t db, uint32_t bars, uint32_t rbar, bool rel) {
  mbar_wait(bars + 8 * (B_FULL2 + S), ph);
  wg_fence();
#pragma unroll
  for (int k = 0; k < 4; k++)
    wgmma_ss_n144<0, TB>(acc, da + (S * (G2_STAGE >> 4) + 2 * k), db + (S * (G2_STAGE >> 4) + (TB ? 128 * k : 2 * k)), 1);
  wg_commit();
  if (!FIRST) {
    wg_wait<1>();
    if (rel) mbar_arrive_at(rbar + 8 * (B_EMPTY2 + PREV));
  }
}
template <int TB, int S0, int N>
__device__ __forceinline__ void g2_run(float (&acc)[72], uint32_t& ph, uint64_t& da, uint64_t& db, uint32_t bars, uint32_t rbar, bool rel, uint32_t zero) {
  if constexpr (N > 0) {
    if constexpr (S0 == 0 && N >= 5) {
#pragma unroll 1
      for (int i = 0; i < N / 5; i++) {
        g2_step<TB, 0>(acc, ph, da, db, bars, rbar, rel);
        g2_step<TB, 1>(acc, ph, da, db, bars, rbar, rel);
        g2_step<TB, 2>(acc, ph, da, db, bars, rbar, rel);
        g2_step<TB, 3>(acc, ph, da, db, bars, rbar, rel);
        g2_step<TB, 4>(acc, ph, da, db, bars, rbar, rel);
        ph ^= 1;
        da += zero; db += zero;
        if (threadIdx.x == 0) TL(0, 20 + (TB ? (N > 25 ? 0 : 16) : 12) + i);
      }
      g2_run<TB, 0, N % 5>(acc, ph, da, db, bars, rbar, rel, zero);
    } else {
      g2_step<TB, S0>(acc, ph, da, db, bars, rbar, rel);
      da += zero; db += zero;
      if (S0 == 4) ph ^= 1;
      g2_run<TB, (S0 + 1) % 5, N - 1>(acc, ph, da, db, bars, rbar, rel, zero);
    }
  }
}

__device__ __forceinline__ void st_tagged(unsigned long long* p, float re, float im, uint32_t tag) {
  asm volatile("st.relaxed.gpu.global.v2.b32 [%0], {%1, %2};" ::"l"(p), "r"((__float_as_uint(re) & ~3u) | tag), "r"((__float_as_uint(im) & ~3u) | tag) : "memory");
}
template <int N>
__device__ __forceinline__ void ld_tagged(float2 (&v)[N], const unsigned long long* p, int stride, int first, uint32_t tag) {
  uint32_t it = 0;
  while (true) {
    uint32_t a[N], b[N], bad = 0;
#pragma unroll
    for (int n = 0; n < N; n++) {
      a[n] = b[n] = tag;
      if (n >= first) asm volatile("ld.relaxed.gpu.global.v2.b32 {%0, %1}, [%2];" : "=r"(a[n]), "=r"(b[n]) : "l"(p + n * stride) : "memory");
    }
#pragma unroll
    for (int n = 0; n < N; n++) {
      bad |= (a[n] ^ tag) | (b[n] ^ tag);
      v[n] = make_float2(__uint_as_float(a[n] & ~3u), __uint_as_float(b[n] & ~3u));
    }
    if (__all_sync(0xffffffff, (bad & 3u) == 0)) break;
    __nanosleep(300);
    if (++it > SPIN_LIMIT) asm volatile("trap;");
  }
}
struct GluConst { float k0, k1, q0, q1; };
__device__ __forceinline__ GluConst glu_const(float rs0, float rs1) {
  return {-1.4426950408889634f * rs0, -1.4426950408889634f * rs1, rcp(rs0 * rs0), rcp(rs1 * rs1)};
}
__device__ __forceinline__ float tanh_fast(float v) { float r; asm("tanh.approx.f32 %0, %1;" : "=f"(r) : "f"(v)); return r; }
template <int J0>
__device__ __forceinline__ void glu_piece(const float (&acc)[64], const GluConst& c, uint32_t (&h)[16]) {
#pragma unroll
  for (int j = J0; j < J0 + 4; j++) {
    const float kk = (j & 1) ? c.k1 : c.k0, qq = (j & 1) ? c.q1 : c.q0;
    const float g0 = acc[2 * j], g1 = acc[2 * j + 1];
    const float v0 = g0 * acc[32 + 2 * j] * rcp(fmaf(ex2(g0 * kk), qq, qq));
    const float v1 = g1 * acc[33 + 2 * j] * rcp(fmaf(ex2(g1 * kk), qq, qq));
    h[j] = pack_bf16(v0, v1);
  }
}
__device__ __forceinline__ void glu_store(const uint32_t (&h)[16], uint32_t base, uint32_t bars, int w, int wq, int lane, int use) {
  wait_count(bars + 8 * B_STGD, use + w - 1);
  const uint32_t dst = base + OFF_STG + w * 8192 + (wq * 16 + (lane & 15)) * 128;
#pragma unroll
  for (int j = 0; j < 4; j++)
    asm volatile("stmatrix.sync.aligned.m8n8.x4.shared.b16 [%0], {%1, %2, %3, %4};"
                 ::"r"(dst + (((2 * j + (lane >> 4)) ^ (lane & 7)) << 4)), "r"(h[4 * j]), "r"(h[4 * j + 1]), "r"(h[4 * j + 2]), "r"(h[4 * j + 3]) : "memory");
  fence_async_smem();
  __syncwarp();
  if (lane == 0) mbar_arrive(bars + 8 * (B_STGF + w));
}

__global__ void __launch_bounds__(384, 1) fused_kernel(const __grid_constant__ Params p) {
  extern __shared__ __align__(1024) uint8_t smem_raw[];
  const uint32_t base = smem_u32(smem_raw);
  const uint32_t bars = base + OFF_BAR;
  uint32_t rank;
  asm("mov.u32 %0, %%cluster_ctarank;" : "=r"(rank));
  if (threadIdx.x == 256) prefetch_map(&p.tm_x);
  const int cl = p.lid[blockIdx.x >> 1];
  const int cta = 2 * cl + rank;
  const int nseq = p.nseq[cl] + p.zero;
  if (nseq == 0) return;
  const int g2tile = p.g2tile[cl];
  const int warp_id = __shfl_sync(0xffffffff, threadIdx.x >> 5, 0);

  Ring ring;
  ring.base = base + OFF_RING;
  ring.l = 0;
  ring.rot = (nseq & 3);

  if (warp_id == 8) {
    const int lane = lane_id();
    if (lane == 0) {
#pragma unroll
      for (int i = 0; i < 4; i++) mbar_init(bars + 8 * (B_FULL1 + i), 1);
      asm volatile("fence.mbarrier_init.release.cluster;" ::: "memory");
    }
    __syncwarp();
    const int mt = 2 * (cl < 64 ? cl & 7 : 4 * (cl - 64)) + rank;
#pragma unroll
    for (int j = 0; j < 3; j++) {
      const uint32_t ptr = ring.base + ((j + ring.rot) & 3) * G1_STAGE;
      e_expect_tx(bars + 8 * (B_FULL1 + j), G1_STAGE);
#pragma unroll
      for (int k = 0; k < 3; k++) e_tma(ptr + k * 16384, &p.tm_x, bars + 8 * (B_FULL1 + j), (3 * j + k) * 64, mt * 128);
    }
    if (lane == 0) {
      TL(2, 61);
      prefetch_map(rank ? &p.tm_w3 : &p.tm_w1);
      prefetch_map(rank ? &p.tm_bim : &p.tm_bre);
    }
  } else if (threadIdx.x == 0) {
#pragma unroll
    for (int i = 0; i < 4; i++) mbar_init(bars + 8 * (B_EMPTY1 + i), 4);
#pragma unroll
    for (int i = 0; i < 5; i++) { mbar_init(bars + 8 * (B_FULL2 + i), 1); mbar_init(bars + 8 * (B_EMPTY2 + i), 4); }
#pragma unroll
    for (int i = 0; i < 2; i++) mbar_init(bars + 8 * (B_STGF + i), 4);
    asm volatile("st.shared.u32 [%0], 0;" ::"r"(bars + 8 * B_STGD) : "memory");
    asm volatile("fence.mbarrier_init.release.cluster;" ::: "memory");
  }
  __syncthreads();
  cluster_arrive();

  if (warp_id >= 8) {
    asm volatile("setmaxnreg.dec.sync.aligned.u32 56;");
    const int lane = lane_id();
    const unsigned epoch = g_epoch[blockIdx.x];
    if (warp_id == 8) {
      ring.ph = 1;
      int mt = 0;
      for (int i = 0; i < nseq; i++) {
        const int e = p.seq[cl][i];
        if (e & 0x80) {
          mt = 2 * (e & 7) + rank;
          for (int j = 0; j < 3; j++) {
            if (i > 0) {
              const uint32_t fb = bars + 8 * (B_FULL1 + ring.l);
              mbar_wait(bars + 8 * (B_EMPTY1 + ring.l), ring.ph);
              e_expect_tx(fb, G1_STAGE);
#pragma unroll
              for (int k = 0; k < 3; k++) e_tma(ring.ptr() + k * 16384, &p.tm_x, fb, (3 * j + k) * 64, mt * 128);
            }
            ring.next();
          }
          if (i == 0) cluster_wait();
        } else {
          if (g2tile >= 0 && i == nseq - PF_G2) {
            e_prefetch(p.w2 + (size_t)(cta - 64) * 12 * DM, 12 * DM * 2);
            e_prefetch(p.x + (size_t)(mt * 128 + g2tile * 32) * DM, 32 * DM * 2);
            e_prefetch(p.dskip, DM * 2);
          }
          for (int j = 0; j < 3; j++) {
            const uint32_t fb = bars + 8 * (B_FULL1 + ring.l);
            mbar_wait(bars + 8 * (B_EMPTY1 + ring.l), ring.ph);
            e_expect_tx(fb, G1_STAGE);
            if (e < NGLU) {
              e_tma_mc(ring.ptr() + rank * 24576, rank ? &p.tm_w3 : &p.tm_w1, fb, e * 64, j * 192);
            } else {
#pragma unroll
              for (int k = 0; k < 3; k++)
                e_tma_mc(ring.ptr() + k * 16384 + rank * 8192, rank ? &p.tm_bim : &p.tm_bre, fb, (3 * j + k) * 64, (e - NGLU) * 64);
            }
            ring.next();
          }
        }
      }
      if (g2tile >= 0) {
        const unsigned target = 2 * (epoch + 1);
        const unsigned* flags = g_flag + mt * 96;
        const uint8_t* hsrc = reinterpret_cast<const uint8_t*>(g_h) + (size_t)mt * NCHUNK * 16384;
        const CUtensorMap* tw2 = &p.tm_w2[g2tile];
        const int col = g2tile * G2N;
        if (lane == 0) { prefetch_map(tw2); prefetch_map(&p.tm_x16); prefetch_map(&p.tm_cp); }
        __syncwarp();
        int ready = 0;
        uint32_t s = 0, ph = 1, st = base + OFF_RING;
        auto next = [&] { st += G2_STAGE; if (++s == 5) { s = 0; ph ^= 1; st = base + OFF_RING; } };
        uint32_t pend = 0;
        int pbase = -1;
        auto check = [&](int c, int end) {
          if (pbase >= 0) {
            const uint32_t m = ~__ballot_sync(0xffffffff, (int)(pend - target) >= 0);
            asm volatile("fence.acquire.gpu;\nfence.proxy.async.global;" ::: "memory");
            ready = pbase + (m ? __ffs(m) - 1 : 32);
            pbase = -1;
          }
          if (c >= ready) {
            const uint32_t m = ~poll_flags<false>(flags + min(c + lane, end - 1), target);
            ready = c + (m ? __ffs(m) - 1 : 32);
          }
        };
        auto sample = [&](int c, int end) {
          if (ready - c <= LOOKAHEAD && ready < end) {
            pbase = ready;
            asm volatile("ld.relaxed.gpu.global.u32 %0, [%1];" : "=r"(pend) : "l"(flags + min(ready + lane, end - 1)) : "memory");
          }
        };
        mbar_wait(bars + 8 * (B_EMPTY1 + ring.l), ring.ph);
        ring.next();
        e_expect_tx(bars + 8 * B_FULL2, 2 * 16384 + 4096 + G2N * 2);
        e_bulk_ld(st + 36864, p.dskip + col, G2N * 2, bars + 8 * B_FULL2);
        e_tma(st, &p.tm_x, bars + 8 * B_FULL2, col, mt * 128);
        e_tma(st + 16384, &p.tm_x, bars + 8 * B_FULL2, col + 64, mt * 128);
        e_tma(st + 32768, &p.tm_x16, bars + 8 * B_FULL2, col + 128, mt * 128);
        next();
        check(0, NGLU);
#pragma unroll 1
        for (int c = 0; c < 3; c++) {
          mbar_wait(bars + 8 * (B_EMPTY1 + ring.l), ring.ph);
          ring.next();
          check(c, NGLU);
          e_g2_glu(st, st + 16384 + rank * 4096, bars + 8 * (B_FULL2 + s), hsrc + (size_t)c * 16384, tw2, col, c * 64 + rank * 32);
          if (lane == 0) TL(3, 31 + c);
          next();
        }
#pragma unroll 1
        for (int c = 3; c < SEG1; c++) {
          mbar_wait(bars + 8 * (B_EMPTY2 + s), ph);
          check(c, NGLU);
          e_g2_glu(st, st + 16384 + rank * 4096, bars + 8 * (B_FULL2 + s), hsrc + (size_t)c * 16384, tw2, col, c * 64 + rank * 32);
          if (lane == 0 && c < 28) TL(3, 31 + c);
          sample(c, NGLU);
          next();
        }
        poll_flags<true>(g_cflag + min(lane, 17), 64 * (epoch + 1));
#pragma unroll 1
        for (int c = 0; c < 18; c++) {
          mbar_wait(bars + 8 * (B_EMPTY2 + s), ph);
          e_g2_ssm(st, st + 16384 + rank * (G2N / 2 * 128), bars + 8 * (B_FULL2 + s), hsrc + (size_t)(NGLU + c) * 16384, &p.tm_cp,
                   c * 64, col + rank * (G2N / 2));
          next();
        }
        check(0, NGLU);
        sample(ready, NGLU);
#pragma unroll 1
        for (int c = SEG1; c < NGLU; c++) {
          mbar_wait(bars + 8 * (B_EMPTY2 + s), ph);
          check(c, NGLU);
          e_g2_glu(st, st + 16384 + rank * 4096, bars + 8 * (B_FULL2 + s), hsrc + (size_t)c * 16384, tw2, col, c * 64 + rank * 32);
          sample(c, NGLU);
          next();
        }
      }
      cluster_arrive();
      cluster_wait();
      if (lane == 0) g_epoch[blockIdx.x] = epoch + 1;
    } else {
      const uint32_t tag = epoch % 3 + 1;
      cluster_wait();
      if (warp_id < 11 && cl < 64) {
        const int hw = warp_id - 9;
        const int wk = cta * 2 + hw;
        const int nit = (wk >> 6) == 1 ? 3 : 2;
        const int seg = wk & 31;
#pragma unroll 1
        for (int r = 0; r < nit; r++) {
          const int item = r < 2 ? wk + 256 * r : wk + 448;
          const int ch = (item >> 5) * 32 + lane;
          const __nv_bfloat16 lre = p.lam_re[ch], lim = p.lam_im[ch], ldt = p.log_dt[ch];
          const int o = seg * 18 * DM + ch;
          __nv_bfloat16 a[18], b[18];
#pragma unroll
          for (int d = 0; d < 18; d++) { a[d] = p.c_re[o + d * DM]; b[d] = p.c_im[o + d * DM]; }
          const float re = __bfloat162float(lre), im = __bfloat162float(lim);
          const float dt = bf_round(expf(__bfloat162float(ldt)));
          const float mag = expf(dt * re);
          float sn, cs;
          sincosf(dt * im, &sn, &cs);
          const float lr = mag * cs, li = mag * sn;
          const float nr = lr - 1.0f, inv = 2.0f / (re * re + im * im);
          const float cr = (nr * re + li * im) * inv, ci = (li * re - nr * im) * inv;
          g_priv[(item * 4 + 3) * 32 + lane] = make_float2(lr, li);
#pragma unroll
          for (int d = 0; d < 18; d++) {
            const float x = __bfloat162float(a[d]), y = __bfloat162float(b[d]);
            __stcg(g_cp + o + d * DM, pack_bf16(x * cr - y * ci, -(x * ci + y * cr)));
          }
        }
        fence_async_gl();
        __syncwarp();
        if (lane == 0) {
          fence_gpu();
          for (int r = 0; r < nit; r++) red_relaxed(g_cflag + ((r < 2 ? wk + 256 * r : wk + 448) >> 5), 1);
        }
        __syncwarp();
        if (lane == 0) TL(2, 24 * hw);
#pragma unroll 1
        for (int r = 0; r < nit; r++) {
          const int item = r < 2 ? wk + 256 * r : wk + 448;
          const int grp = item >> 5;
          const float2 lam = g_priv[(item * 4 + 3) * 32 + lane];
          poll_flags<true>(g_buflag + (seg >> 1) * 16 + (grp >> 1), epoch + 1);
          if (lane == 0) TL(2, 24 * hw + 1 + 2 * r);
          const unsigned* src = reinterpret_cast<const unsigned*>(g_bu) + (seg * 18 + grp) * 2048 + lane;
          float hr[4] = {}, hi[4] = {};
#pragma unroll
          for (int t0 = 0; t0 < 16; t0 += 8) {
            uint32_t v[8][4];
#pragma unroll
            for (int t = 0; t < 8; t++)
#pragma unroll
              for (int c = 0; c < 4; c++)
                v[t][c] = __ldcg(src + (t0 + t) * 32 + c * 512);
            pin2(v);
#pragma unroll
            for (int t = 0; t < 8; t++)
#pragma unroll
              for (int c = 0; c < 4; c++) {
                const float nr = fmaf(lam.x, hr[c], fmaf(-lam.y, hi[c], bf_lo(v[t][c])));
                hi[c] = fmaf(lam.x, hi[c], fmaf(lam.y, hr[c], bf_hi(v[t][c]))); hr[c] = nr;
              }
          }
          float pr = lam.x, pi = lam.y;
#pragma unroll
          for (int n = 0; n < 4; n++) { const float t = pr * pr - pi * pi; pi = 2.0f * pr * pi; pr = t; }
          float ar = hr[0], ai = hi[0];
#pragma unroll
          for (int c = 1; c < 4; c++) {
            g_priv[(item * 4 + c - 1) * 32 + lane] = make_float2(hr[c - 1], hi[c - 1]);
            const float t = fmaf(pr, ar, fmaf(-pi, ai, hr[c]));
            ai = fmaf(pr, ai, fmaf(pi, ar, hi[c])); ar = t;
          }
          const uint32_t sib = base + OFF_SIB + r * 256 + lane * 8;
          if (hw == 0) asm volatile("st.shared.v2.f32 [%0], {%1, %2};" ::"r"(sib), "f"(ar), "f"(ai) : "memory");
          bar_sync(6, 64);
          if (hw == 1) {
            float br, bi;
            asm volatile("ld.shared.v2.f32 {%0, %1}, [%2];" : "=f"(br), "=f"(bi) : "r"(sib) : "memory");
#pragma unroll
            for (int n = 0; n < 2; n++) { const float t = pr * pr - pi * pi; pi = 2.0f * pr * pi; pr = t; }
            st_tagged(g_agg + (grp * 16 + (seg >> 1)) * 32 + lane, fmaf(pr, br, fmaf(-pi, bi, ar)), fmaf(pr, bi, fmaf(pi, br, ai)), tag);
          }
          if (lane == 0) TL(2, 24 * hw + 2 + 2 * r);
        }
#pragma unroll 1
        for (int r = 0; r < nit; r++) {
          const int item = r < 2 ? wk + 256 * r : wk + 448;
          const float2 lam = g_priv[(item * 4 + 3) * 32 + lane];
          float2 blk[3];
#pragma unroll
          for (int c = 0; c < 3; c++) blk[c] = g_priv[(item * 4 + c) * 32 + lane];
          float2 v[15];
          ld_tagged<15>(v, g_agg + ((item >> 5) * 16 + (seg >> 1) - 15) * 32 + lane, 32, 15 - (seg >> 1), tag);
          float pr = lam.x, pi = lam.y;
#pragma unroll
          for (int n = 0; n < 4; n++) { const float t = pr * pr - pi * pi; pi = 2.0f * pr * pi; pr = t; }
          float qr = pr, qi = pi;
#pragma unroll
          for (int n = 0; n < 2; n++) { const float t = qr * qr - qi * qi; qi = 2.0f * qr * qi; qr = t; }
          const float ur = qr * qr - qi * qi, ui = 2.0f * qr * qi;
          float hr = 0.f, hi = 0.f;
#pragma unroll
          for (int n = 0; n < 15; n++) {
            const float t = fmaf(ur, hr, fmaf(-ui, hi, v[n].x));
            hi = fmaf(ur, hi, fmaf(ui, hr, v[n].y)); hr = t;
          }
          if (hw == 1) {
            float br, bi;
            asm volatile("ld.shared.v2.f32 {%0, %1}, [%2];" : "=f"(br), "=f"(bi) : "r"(base + OFF_SIB + r * 256 + lane * 8) : "memory");
            const float t = fmaf(qr, hr, fmaf(-qi, hi, br));
            hi = fmaf(qr, hi, fmaf(qi, hr, bi)); hr = t;
          }
          float2 h[4];
          h[0] = make_float2(hr, hi);
#pragma unroll
          for (int c = 1; c < 4; c++)
            h[c] = make_float2(fmaf(pr, h[c - 1].x, fmaf(-pi, h[c - 1].y, blk[c - 1].x)), fmaf(pr, h[c - 1].y, fmaf(pi, h[c - 1].x, blk[c - 1].y)));
          if (lane == 0) TL(2, 24 * hw + 7 + r);
          const unsigned* src = reinterpret_cast<const unsigned*>(g_bu) + (seg * 18 + (item >> 5)) * 2048 + lane;
          uint8_t* dst = reinterpret_cast<uint8_t*>(g_h) + (size_t)((seg >> 1) * NCHUNK + NGLU + (item >> 5)) * 16384 + (seg & 1) * 8192;
#pragma unroll
          for (int t0 = 0; t0 < 16; t0 += 8) {
            uint32_t u[8][4];
#pragma unroll
            for (int t = 0; t < 8; t++)
#pragma unroll
              for (int c = 0; c < 4; c++) u[t][c] = __ldcg(src + (t0 + t) * 32 + c * 512);
            pin2(u);
#pragma unroll
            for (int t = 0; t < 8; t++) {
              unsigned* d = reinterpret_cast<unsigned*>(dst + (uint32_t)((lane * 4) ^ (t << 4)));
#pragma unroll
              for (int c = 0; c < 4; c++) {
                const float nr = fmaf(lam.x, h[c].x, fmaf(-lam.y, h[c].y, bf_lo(u[t][c])));
                const float ni = fmaf(lam.x, h[c].y, fmaf(lam.y, h[c].x, bf_hi(u[t][c])));
                h[c].x = nr; h[c].y = ni;
                d[(t0 + t) * 32 + c * 512] = pack_bf16(nr, ni);
              }
            }
          }
          if (lane == 0) TL(2, 24 * hw + 10 + r);
        }
        fence_async_gl();
        __syncwarp();
        if (lane == 0) {
          fence_gpu();
          for (int r = 0; r < nit; r++) red_relaxed(g_cflag + ((r < 2 ? wk + 256 * r : wk + 448) >> 5), 1);
          TL(2, 24 * hw + 13);
        }
        __syncwarp();
      }
      if (warp_id == 11 && lane == 0) {
        uint32_t use = 0;
        int mt = 0;
        for (int i = 0; i < nseq; i++) {
          const int e = p.seq[cl][i];
          if (e & 0x80) { mt = 2 * (e & 7) + rank; continue; }
          const int nh = e < NGLU ? 1 : 2;
          for (int w = 0; w < 2; w++) {
            for (int h = 0; h < nh; h++) {
              uint8_t* dst = e < NGLU ? reinterpret_cast<uint8_t*>(g_h) + (size_t)(mt * NCHUNK + e) * 16384 + w * 8192
                                      : reinterpret_cast<uint8_t*>(g_bu) + (size_t)((2 * mt + w) * 18 + 2 * (e - NGLU) + h) * 8192;
              mbar_wait(bars + 8 * (B_STGF + ((use + h) & 1)), (use >> 1) & 1);
              asm volatile("cp.async.bulk.global.shared::cta.bulk_group [%0], [%1], 8192;" ::"l"(dst), "r"(base + OFF_STG + ((use + h) & 1) * 8192) : "memory");
            }
            asm volatile("cp.async.bulk.commit_group;" ::: "memory");
            asm volatile("cp.async.bulk.wait_group 0;" ::: "memory");
            use += nh;
            asm volatile("st.release.cta.shared.u32 [%0], %1;" ::"r"(bars + 8 * B_STGD), "r"(use) : "memory");
            TL(3, 3 * i + w);
          }
          if (e < NGLU) red_release(g_flag + mt * 96 + e, 2);
          else red_release(g_buflag + mt * 16 + e - NGLU, 1);
          TL(3, 3 * i + 2);
        }
      }
      __syncwarp();
      cluster_arrive();
      cluster_wait();
    }
  } else {
    asm volatile("setmaxnreg.inc.sync.aligned.u32 224;");
    const int lane = lane_id();
    const int w = warp_id >> 2, wq = warp_id & 3;
    const int g = lane >> 2, q = lane & 3;
    const bool rel = lane == 0 && wq < 2;
    const uint32_t rbar = map_cta(bars, wq & 1);
    ring.ph = 0;
    float mean0 = 0.f, mean1 = 0.f, rs0 = 0.f, rs1 = 0.f;
    int mt = 0;
    cluster_wait();
    float acc[64];
    int use = 0;
    {
      uint32_t a[128];
#pragma unroll
      for (int i = 0; i < 64; i++) acc[i] = 0.f;
      const int nloop = nseq - (g2tile >= 0);
      for (int i = 0; i < nloop; i++) {
        const int e = p.seq[cl][i];
        if (e & 0x80) {
          mt = 2 * (e & 7) + rank;
          float cs[2][4] = {}, c0[2][4] = {}, c1[2][4] = {};
          const uint32_t off = (w * 64 + wq * 16 + (lane & 15)) * 128;
          uint32_t l8[16], pv0 = 0, pv1 = 0;
#pragma unroll
          for (int j = 0; j < 3; j++) {
            mbar_wait(bars + 8 * (B_FULL1 + ring.l), ring.ph);
            if (threadIdx.x == 0) TL(2, 58 + j);
#pragma unroll
            for (int k = 0; k < 12; k++) {
              const int s = j * 12 + k;
              uint32_t* f = s < 32 ? &a[4 * s] : &l8[4 * (s - 32)];
              asm volatile("ldmatrix.sync.aligned.m8n8.x4.shared.b16 {%0, %1, %2, %3}, [%4];"
                           : "=r"(f[0]), "=r"(f[1]), "=r"(f[2]), "=r"(f[3])
                           : "r"(ring.ptr() + (k >> 2) * 16384 + off + (((2 * (k & 3) + (lane >> 4)) ^ (lane & 7)) << 4)) : "memory");
            }
            if (j == 0) {
              pv0 = __byte_perm(__shfl_sync(0xffffffff, a[0], lane & ~3), 0, 0x1010);
              pv1 = __byte_perm(__shfl_sync(0xffffffff, a[1], lane & ~3), 0, 0x1010);
            }
#pragma unroll
            for (int k = 0; k < 12; k++) {
              const int s = j * 12 + k;
              const uint32_t* f = s < 32 ? &a[4 * s] : &l8[4 * (s - 32)];
              mma16816(cs[k & 1], f[0], f[1], f[2], f[3], 0x3f803f80u, 0x3f803f80u);
              const uint32_t e0 = sub_bf16x2(f[0], pv0), e1 = sub_bf16x2(f[1], pv1), e2 = sub_bf16x2(f[2], pv0), e3 = sub_bf16x2(f[3], pv1);
              mma16816(c0[k & 1], e0, e1, e2, e3, e0, e2);
              mma16816(c1[k & 1], e0, e1, e2, e3, e1, e3);
              if (k == 0) {
                bar_sync(3 + w, 128);
                if (rel) mbar_arrive_at(rbar + 8 * (B_EMPTY1 + ring.l));
              }
            }
            ring.next();
          }
          const float mu0 = (cs[0][0] + cs[1][0]) * (1.0f / DM), mu1 = (cs[0][2] + cs[1][2]) * (1.0f / DM);
          mean0 = bf_round(mu0); mean1 = bf_round(mu1);
          const uint32_t m0 = pack_bf16(mean0, mean0), m1 = pack_bf16(mean1, mean1);
#pragma unroll
          for (int n = 0; n < 16; n++) l8[n] = sub_bf16x2(l8[n], (n & 1) ? m1 : m0);
#pragma unroll
          for (int k = 0; k < 4; k++)
            asm volatile("stmatrix.sync.aligned.m8n8.x4.shared.b16 [%0], {%1, %2, %3, %4};"
                         ::"r"(base + OFF_XA + off + (((2 * k + (lane >> 4)) ^ (lane & 7)) << 4)), "r"(l8[4 * k]), "r"(l8[4 * k + 1]), "r"(l8[4 * k + 2]), "r"(l8[4 * k + 3]) : "memory");
          {
            const int src = (lane & ~3) | (g >> 1);
            const float q0 = __shfl_sync(0xffffffff, (g & 1) ? c0[0][1] + c0[1][1] : c0[0][0] + c0[1][0], src);
            const float q1 = __shfl_sync(0xffffffff, (g & 1) ? c1[0][3] + c1[1][3] : c1[0][2] + c1[1][2], src);
            const float t0 = mu0 - bf_lo(pv0), t1 = mu1 - bf_lo(pv1);
            const float v0 = bf_round(fmaxf(q0 * (1.0f / DM) - t0 * t0, 0.f)), v1 = bf_round(fmaxf(q1 * (1.0f / DM) - t1 * t1, 0.f));
            rs0 = rcp(bf_round(sqrt_fast(bf_round(v0 + 1e-5f))));
            rs1 = rcp(bf_round(sqrt_fast(bf_round(v1 + 1e-5f))));
          }
#pragma unroll
          for (int n = 0; n < 128; n++) a[n] = sub_bf16x2(a[n], (n & 1) ? m1 : m0);
          pin(a);
          fence_async_smem();
          bar_sync(3 + w, 128);
          if (threadIdx.x % 128 == 0) TL(w, 0);
          if (threadIdx.x == 0) TG(2, 24);
          continue;
        }
        if (!(i == 1 && w == 0)) bar_sync(1 + w, 256);
        if (e < NGLU) g1_mainloop<1>(acc, a, ring, bars, base + OFF_XA + w * 8192, w, rel, rbar, 3 * i - 1);
        else g1_mainloop<0>(acc, a, ring, bars, base + OFF_XA + w * 8192, w, rel, rbar, 3 * i - 1);
        if (threadIdx.x % 128 == 0) TL(w, 3 * i);
        if (threadIdx.x == 0) TG(2, 24 + i);
        if (e < NGLU) {
          const GluConst gc = glu_const(rs0, rs1);
          uint32_t h[16];
          glu_piece<0>(acc, gc, h); glu_piece<4>(acc, gc, h); glu_piece<8>(acc, gc, h); glu_piece<12>(acc, gc, h);
          glu_store(h, base, bars, w, wq, lane, use);
          use += 2;
        } else {
#pragma unroll
          for (int hh = 0; hh < 2; hh++) {
            const uint32_t dst = base + OFF_STG + hh * 8192 + (wq * 16 + g) * 128 + (q & 1) * 8;
            uint32_t v[16];
#pragma unroll
            for (int j = 0; j < 4; j++) {
              const int n = 16 * hh + 4 * j;
              v[4 * j] = pack_bf16(acc[n] * rs0, acc[32 + n] * rs0);
              v[4 * j + 1] = pack_bf16(acc[n + 1] * rs0, acc[33 + n] * rs0);
              v[4 * j + 2] = pack_bf16(acc[n + 2] * rs1, acc[34 + n] * rs1);
              v[4 * j + 3] = pack_bf16(acc[n + 3] * rs1, acc[35 + n] * rs1);
            }
            wait_count(bars + 8 * B_STGD, use + 2 * w + hh - 1);
#pragma unroll
            for (int j = 0; j < 4; j++) {
              const uint32_t ch = (2 * j + (q >> 1)) << 4;
              asm volatile("st.shared.v2.u32 [%0], {%1, %2};" ::"r"(dst + ch), "r"(v[4 * j]), "r"(v[4 * j + 1]) : "memory");
              asm volatile("st.shared.v2.u32 [%0], {%1, %2};" ::"r"(dst + ch + 8 * 128), "r"(v[4 * j + 2]), "r"(v[4 * j + 3]) : "memory");
            }
            fence_async_smem();
            __syncwarp();
            if (lane == 0) mbar_arrive(bars + 8 * (B_STGF + hh));
          }
          use += 4;
        }
        if (threadIdx.x % 128 == 0) TL(w, 3 * i + 1);
      }
      if (g2tile >= 0) {
        bar_sync(1 + w, 256);
        g1_mainloop<1>(acc, a, ring, bars, base + OFF_XA + w * 8192, w, rel, rbar, 3 * nloop - 1);
        if (threadIdx.x % 128 == 0) TL(w, 3 * nloop);
        if (w == 0) {
          const GluConst gc = glu_const(rs0, rs1);
          uint32_t h[16];
          glu_piece<0>(acc, gc, h); glu_piece<4>(acc, gc, h); glu_piece<8>(acc, gc, h); glu_piece<12>(acc, gc, h);
          glu_store(h, base, bars, w, wq, lane, use);
        }
      }
    }
    if (g2tile >= 0) {
      float o[72], bias[72];
      uint32_t f[36], dk[18];
      auto load_x = [&] {
        const uint32_t row = w * 64 + wq * 16 + (lane & 15);
        const uint32_t st = base + OFF_RING;
        mbar_wait(bars + 8 * B_FULL2, 0);
#pragma unroll
        for (int k = 0; k < 9; k++) {
          const uint32_t src = st + (k < 8 ? (k >> 2) * 16384 + row * 128 + (((2 * (k & 3) + (lane >> 4)) ^ (lane & 7)) << 4)
                                           : 32768 + row * 32 + ((lane >> 4) << 4));
          asm volatile("ldmatrix.sync.aligned.m8n8.x4.shared.b16 {%0, %1, %2, %3}, [%4];"
                       : "=r"(f[4 * k]), "=r"(f[4 * k + 1]), "=r"(f[4 * k + 2]), "=r"(f[4 * k + 3]) : "r"(src) : "memory");
        }
#pragma unroll
        for (int j = 0; j < 18; j++) asm volatile("ld.shared.u32 %0, [%1];" : "=r"(dk[j]) : "r"(st + 36864 + j * 16 + q * 4) : "memory");
        pin(f);
        pin(dk);
        bar_sync(3 + w, 128);
        if (rel) mbar_arrive_at(rbar + 8 * B_EMPTY2);
      };
      auto piece = [&](float (&b)[72], int n0, int n1) {
#pragma unroll
        for (int n = n0; n < n1; n++) {
          const float m = (n & 1) ? mean1 : mean0, rs = (n & 1) ? rs1 : rs0;
          const float x0 = bf_lo(f[n]), x1 = bf_hi(f[n]);
          b[2 * n] = fmaf(x0 - m, rs * bf_lo(dk[n >> 1]), x0);
          b[2 * n + 1] = fmaf(x1 - m, rs * bf_hi(dk[n >> 1]), x1);
          asm volatile("" : "+f"(b[2 * n]), "+f"(b[2 * n + 1])::"memory");
        }
      };
      uint32_t ph = 0;
      uint64_t da = make_desc(base + OFF_RING + w * 8192, 16, 1024);
      uint64_t dbn = make_desc(base + OFF_RING + 16384, 8192, 1024);
      const uint32_t zero = nseq >> 8;
      load_x();
      if (w == 0) {
        piece(o, 0, 36);
        pin(o);
        bar_sync(1, 256);
        g2_step<1, 1, true>(o, 0, da, dbn, bars, rbar, rel);
      } else {
        mbar_wait(bars + 8 * (B_FULL2 + 1), 0);
        wg_fence();
        wgmma_ss_n144_init<0, 1>(o, da + (G2_STAGE >> 4), dbn + (G2_STAGE >> 4));
#pragma unroll
        for (int k = 1; k < 4; k++) wgmma_ss_n144<0, 1>(o, da + ((G2_STAGE >> 4) + 2 * k), dbn + ((G2_STAGE >> 4) + 128 * k), 1);
        wg_commit();
      }
      if (threadIdx.x % 128 == 0) TL(w, 54);
#pragma unroll
      for (int i = 0; i < 72; i++) bias[i] = 0.f;
      {
        const GluConst gc = glu_const(rs0, rs1);
        uint32_t h[16];
        if (threadIdx.x % 128 == 0) TL(w, 40);
        if (w == 1) { glu_piece<0>(acc, gc, h); pin(h); }
        da += zero; dbn += zero;
        g2_step<1, 2>(o, 0, da, dbn, bars, rbar, rel);
        if (threadIdx.x % 128 == 0) TL(w, 41);
        if (w == 1) { glu_piece<4>(acc, gc, h); pin(h); }
        da += zero; dbn += zero;
        g2_step<1, 3>(o, 0, da, dbn, bars, rbar, rel);
        if (threadIdx.x % 128 == 0) TL(w, 42);
        if (w == 1) { glu_piece<8>(acc, gc, h); pin(h); }
        da += zero; dbn += zero;
        g2_step<1, 4>(o, 0, da, dbn, bars, rbar, rel);
        if (threadIdx.x % 128 == 0) TL(w, 43);
        if (w == 1) {
          glu_piece<12>(acc, gc, h);
          wg_wait<0>();
          if (rel) mbar_arrive_at(rbar + 8 * (B_EMPTY2 + 4));
          glu_store(h, base, bars, w, wq, lane, use);
        }
        da += zero; dbn += zero;
        g2_step<1, 0>(o, 1, da, dbn, bars, rbar, rel && w == 0);
        if (threadIdx.x % 128 == 0) TL(w, 17);
      }
#define G2_PIECE(S, PH, N0) da += zero; dbn += zero; g2_step<1, S>(o, PH, da, dbn, bars, rbar, rel); if (w == 1) piece(bias, N0, N0 + 4);
      G2_PIECE(1, 1, 0) G2_PIECE(2, 1, 4) G2_PIECE(3, 1, 8) G2_PIECE(4, 1, 12)
      G2_PIECE(0, 0, 16) G2_PIECE(1, 0, 20) G2_PIECE(2, 0, 24) G2_PIECE(3, 0, 28) G2_PIECE(4, 0, 32)
      ph = 1;
      if (threadIdx.x % 128 == 0) TL(w, 55);
      if (threadIdx.x == 0) TG(2, 41);
      g2_run<1, 0, SEG1 - 14>(o, ph, da, dbn, bars, rbar, rel, zero);
      if (threadIdx.x % 128 == 0) TL(w, 56);
      if (threadIdx.x == 0) TG(2, 42);
      dbn -= (uint64_t)((8192 - 16) >> 4) << 16;
      g2_run<0, (SEG1 + 1) % 5, 18>(o, ph, da, dbn, bars, rbar, rel, zero);
      dbn += (uint64_t)((8192 - 16) >> 4) << 16;
      if (threadIdx.x % 128 == 0) TL(w, 57);
      if (threadIdx.x == 0) TG(2, 43);
      g2_run<1, (SEG1 + 19) % 5, NGLU - SEG1 - 4>(o, ph, da, dbn, bars, rbar, rel, zero);
      if (w == 1) {
        wg_wait<0>();
        bar_arrive(7, 256);
        pin(o);
#pragma unroll
        for (int i = 0; i < 72; i++) o[i] += bias[i];
        pin(o);
        bar_sync(2, 256);
      }
      g2_run<1, 2, 4>(o, ph, da, dbn, bars, rbar, false, zero);
      if (w == 0) bar_arrive(2, 256);
      cluster_arrive();
      wg_wait<0>();
      pin(o);
      if (threadIdx.x % 128 == 0) TL(w, 58);
      if (threadIdx.x == 0) TG(2, 44);
      if (w == 0) { bar_sync(7, 256); bar_arrive(8, 256); } else bar_sync(8, 256);
      const uint32_t ob = base + OFF_RING + (1 + w) * G2_STAGE + wq * 16 * OUT_PITCH;
#pragma unroll
      for (int j = 0; j < 18; j++) {
        asm volatile("st.shared.v2.f32 [%0], {%1, %2};" ::"r"(ob + g * OUT_PITCH + j * 32 + q * 8),
                     "f"(o[4 * j]), "f"(o[4 * j + 1]) : "memory");
        asm volatile("st.shared.v2.f32 [%0], {%1, %2};" ::"r"(ob + (g + 8) * OUT_PITCH + j * 32 + q * 8),
                     "f"(o[4 * j + 2]), "f"(o[4 * j + 3]) : "memory");
      }
      fence_async_smem();
      __syncwarp();
      if (lane < 16) {
        float* op = p.out + (size_t)(mt * 128 + w * 64 + wq * 16 + lane) * DM + g2tile * G2N;
        asm volatile("cp.async.bulk.global.shared::cta.bulk_group [%0], [%1], %2;" ::"l"(op), "r"(ob + lane * OUT_PITCH), "n"(G2N * 4) : "memory");
        asm volatile("cp.async.bulk.commit_group;" ::: "memory");
        asm volatile("cp.async.bulk.wait_group.read 0;" ::: "memory");
      }
      __syncwarp();
      if (threadIdx.x % 128 == 0) TL(w, 59);
    } else {
      cluster_arrive();
      if (w == 0) bar_sync(1, 256);
    }
    cluster_wait();
  }
}

typedef CUresult (*EncodeFn)(CUtensorMap*, CUtensorMapDataType, cuuint32_t, void*, const cuuint64_t*, const cuuint64_t*,
                             const cuuint32_t*, const cuuint32_t*, CUtensorMapInterleave, CUtensorMapSwizzle,
                             CUtensorMapL2promotion, CUtensorMapFloatOOBfill);

void make_map(EncodeFn enc, CUtensorMap* m, const void* ptr, int cols, int rows, int pitch, int boxc, int boxr,
              CUtensorMapSwizzle sw = CU_TENSOR_MAP_SWIZZLE_128B) {
  cuuint64_t gd[2] = {(cuuint64_t)cols, (cuuint64_t)rows};
  cuuint64_t gs[1] = {(cuuint64_t)pitch * 2};
  cuuint32_t bd[2] = {(cuuint32_t)boxc, (cuuint32_t)boxr};
  cuuint32_t es[2] = {1, 1};
  enc(m, CU_TENSOR_MAP_DATA_TYPE_BFLOAT16, 2, const_cast<void*>(ptr), gd, gs, bd, es, CU_TENSOR_MAP_INTERLEAVE_NONE,
      sw, CU_TENSOR_MAP_L2_PROMOTION_L2_256B, CU_TENSOR_MAP_FLOAT_OOB_FILL_NONE);
}

void build_schedule(Params& p) {
  p.zero = 0;
#define SCHED_EXTRA 1
  const char* pat[8] = {
      "SSGGGGGGGGGGGGG", "SGGGGGGGGGGGGGG", "SGGGGGGGGGGGGG", "SGGGGGGGGGGGGG",
      "SGGGG", "SGGGG", "SGGGG", "SGGGG"};
  const int NX = SCHED_EXTRA ? 3 : 0, X0 = NGLU - NX - 6;
  uint8_t unit[8][MAXSEQ];
  int len[8], ng = 0, ns = 0;
  for (int k = 0; k < 8; k++) { len[k] = 0; while (pat[k][len[k]]) len[k]++; }
  for (int t = 0; t < MAXSEQ; t++)
    for (int k = 0; k < 8; k++)
      if (t < len[k]) {
        if (ng == X0) ng += NX;
        unit[k][t] = pat[k][t] == 'S' ? NGLU + ns++ : ng++;
      }
  for (int c = 0; c < NCL; c++) { p.nseq[c] = 0; p.g2tile[c] = -1; }
#define PLACE 1
  for (int c = 0; c < NCL; c++) p.lid[c] = PLACE == 0 ? c : c < 4 ? 28 + c : c < 36 ? 28 + c : c < 64 ? c - 36 : c;
  for (int k = 0; k < 8; k++)
    for (int mp = 0; mp < 8; mp++) {
      const int c = k * 8 + mp;
      p.seq[c][0] = 0x80 | mp;
      for (int t = 0; t < len[k]; t++) p.seq[c][1 + t] = unit[k][t];
      p.nseq[c] = 1 + len[k];
      p.g2tile[c] = k >= 4 ? k - 4 : -1;
    }
  for (int x = 0; x < 2 && NX; x++) {
    const int c = 64 + x;
    int n = 0;
    for (int j = 0; j < 4; j++) {
      p.seq[c][n++] = 0x80 | (4 * x + j);
      for (int u = X0; u < X0 + NX; u++) p.seq[c][n++] = u;
    }
    p.nseq[c] = n;
  }
}

}

extern "C" void kernel_launch(void* const* d_in, const int* in_sizes, int n_in, void* d_out, int out_size) {
  static Params p;
  static EncodeFn enc = nullptr;
  static void* cp_ptr = nullptr;
  if (!enc) {
    void* fn = nullptr;
    cudaDriverEntryPointQueryResult qr;
    cudaGetDriverEntryPoint("cuTensorMapEncodeTiled", &fn, cudaEnableDefault, &qr);
    enc = (EncodeFn)fn;
    cudaFuncSetAttribute(fused_kernel, cudaFuncAttributeMaxDynamicSharedMemorySize, SMEM_BYTES);
    cudaGetSymbolAddress(&cp_ptr, g_cp);
    build_schedule(p);
  }
  make_map(enc, &p.tm_x, d_in[0], DM, SEQ, DM, 64, 128);
  make_map(enc, &p.tm_x16, d_in[0], DM, SEQ, DM, 16, 128, CU_TENSOR_MAP_SWIZZLE_NONE);
  make_map(enc, &p.tm_bre, d_in[3], DM, DM, DM, 64, 64);
  make_map(enc, &p.tm_bim, d_in[4], DM, DM, DM, 64, 64);
  make_map(enc, &p.tm_cp, cp_ptr, 2 * DM, DM, 2 * DM, 64, G2N / 2);
  make_map(enc, &p.tm_w1, d_in[10], FF, DM, FF, 64, 192);
  make_map(enc, &p.tm_w3, d_in[11], FF, DM, FF, 64, 192);
  for (int j = 0; j < 4; j++) make_map(enc, &p.tm_w2[j], d_in[12], G2N * (j + 1), FF, DM, 64, 32);
  p.x = (const __nv_bfloat16*)d_in[0];
  p.w2 = (const __nv_bfloat16*)d_in[12];
  p.c_re = (const __nv_bfloat16*)d_in[5];
  p.c_im = (const __nv_bfloat16*)d_in[6];
  p.lam_re = (const __nv_bfloat16*)d_in[1];
  p.lam_im = (const __nv_bfloat16*)d_in[2];
  p.log_dt = (const __nv_bfloat16*)d_in[7];
  p.dskip = (const __nv_bfloat16*)d_in[8];
  p.out = (float*)d_out;

  cudaLaunchConfig_t cfg = {};
  cfg.gridDim = dim3(2 * NCL);
  cfg.blockDim = dim3(384);
  cfg.dynamicSmemBytes = SMEM_BYTES;
  cfg.stream = cudaStreamPerThread;
  cudaLaunchAttribute at[1];
  at[0].id = cudaLaunchAttributeClusterDimension;
  at[0].val.clusterDim.x = 2; at[0].val.clusterDim.y = 1; at[0].val.clusterDim.z = 1;
  cfg.attrs = at; cfg.numAttrs = 1;
  cudaLaunchKernelEx(&cfg, fused_kernel, p);
}
```
